```python
import torch

def _softmax(x, axis=-1):
    return torch.softmax(x, dim=axis)
def _gelu(x):
    return torch.nn.functional.gelu(x, approximate="tanh")
def _silu(x):
    return torch.nn.functional.silu(x)
def _sigmoid(x):
    return torch.sigmoid(x)
def _layernorm(x, axis=-1, eps=1e-5):
    m = x.mean(dim=axis, keepdim=True)
    v = x.var(dim=axis, keepdim=True, unbiased=False)
    return (x - m) / torch.sqrt(v + eps)
def _scatter_add(tgt, idx, src, axis=0):
    return tgt.clone().index_add_(axis, idx, src)
def _segment_sum(src, seg, n):
    out = torch.zeros((n,) + src.shape[1:], dtype=src.dtype)
    return out.index_add_(0, seg, src)
def _pad(x, pw):
    flat = tuple(v for pair in reversed(pw) for v in pair)
    return torch.nn.functional.pad(x, flat)

kernel_name = 'parallel_sum__sliding_block_cached__swiglu_ffn__decode'

def setup_inputs():

    _w = (lambda a: (lambda t: t.to(torch.bfloat16) if t.is_floating_point() else t)(torch.as_tensor(a)))
    def _A_setup():
        B, Sq, D = 1, 1, 512
        Hq, Hkv, Sk, Dh = 32, 8, 65536, 128
        assert Hq % Hkv == 0, (Hq, Hkv)
        return {
            "x": _w((lambda *s: torch.randn(*s, dtype=torch.bfloat16) * 0.05)(B, Sq, D)),
            "k_cache": _w((lambda *s: torch.randn(*s, dtype=torch.bfloat16) * 3.2)(B, Hkv, Sk, Dh)),
            "v_cache": _w((lambda *s: torch.randn(*s, dtype=torch.bfloat16) * 1.6)(B, Hkv, Sk, Dh)),
            "wq": _w((lambda *s: torch.randn(*s, dtype=torch.bfloat16) * 3.2)(D, Hq * Dh) * (D ** -0.5)),
            "wo": _w((lambda *s: torch.randn(*s, dtype=torch.bfloat16) * 1.6)(Hq * Dh, D) * ((Hq * Dh) ** -0.5)),
        }
    _A_in = _A_setup()

    def _B_setup():
        B, S, D, F = 1, 1, 512, 1792
        return {
            "x": _w((lambda *s: torch.randn(*s, dtype=torch.bfloat16) * 0.05)(B, S, D)),
            "w_gate": _w((lambda *s: torch.randn(*s, dtype=torch.bfloat16) * 0.05)(D, F)),
            "w_up": _w((lambda *s: torch.randn(*s, dtype=torch.bfloat16) * 0.05)(D, F)),
            "w_down": _w((lambda *s: torch.randn(*s, dtype=torch.bfloat16) * 0.05)(F, D)),
        }
    _B_in = _B_setup()

    return {
        "A_x": _A_in["x"],
        "A_k_cache": _A_in["k_cache"],
        "A_v_cache": _A_in["v_cache"],
        "A_wq": _A_in["wq"],
        "A_wo": _A_in["wo"],
        "B_x": _B_in["x"],
        "B_w_gate": _B_in["w_gate"],
        "B_w_up": _B_in["w_up"],
        "B_w_down": _B_in["w_down"],
    }

def reference(A_x, A_k_cache, A_v_cache, A_wq, A_wo, B_x, B_w_gate, B_w_up, B_w_down):
    def _A_ref(x, k_cache, v_cache, wq, wo):
        B, Sq, D = x.shape
        Hq, Dh = 32, 128
        Hkv, Sk = k_cache.shape[1], k_cache.shape[2]
        W = min(4096, max(256, Sk // 4))
        rep = Hq // Hkv
        q = (lambda x, *d: x.permute(*d))((x @ wq).reshape(B, Sq, Hq, Dh), 0, 2, 1, 3)
        k = (lambda x, n, axis: torch.repeat_interleave(x, n, dim=axis))(k_cache[:, :, Sk - W:, :], rep, axis=1)
        v = (lambda x, n, axis: torch.repeat_interleave(x, n, dim=axis))(v_cache[:, :, Sk - W:, :], rep, axis=1)
        scores = torch.einsum("bhqd,bhkd->bhqk", q, k) * (Dh ** -0.5)
        p = _softmax(scores, axis=-1)
        o = torch.einsum("bhqk,bhkd->bhqd", p, v)
        return (lambda x, *d: x.permute(*d))(o, 0, 2, 1, 3).reshape(B, Sq, Hq * Dh) @ wo

    def _B_ref(x, w_gate, w_up, w_down):
        g = _silu(x @ w_gate)
        u = x @ w_up
        return (g * u) @ w_down

    x = A_x
    xn = _layernorm(x, axis=-1)
    return x + _A_ref(xn, A_k_cache, A_v_cache, A_wq, A_wo) + _B_ref(xn, B_w_gate, B_w_up, B_w_down)
```

```cpp
#include <cuda_runtime.h>
#include <cuda_bf16.h>
#include <cuda.h>
#include <stdint.h>

namespace {

constexpr int D_MODEL = 512;
constexpr int HKV     = 8;
constexpr int SK      = 65536;
constexpr int DH      = 128;
constexpr int WIN     = 4096;
constexpr int FF      = 1792;
constexpr int NSPLIT  = 16;
constexpr int KEYS    = WIN / NSPLIT;
constexpr int NCTA    = HKV * NSPLIT;
constexpr int NTHREADS = 576;
constexpr int SPIN_LIMIT = 1 << 20;

constexpr int OFF_K   = 0;
constexpr int OFF_V   = 65536;
constexpr int OFF_WO  = 131072;
constexpr int OFF_WD  = OFF_WO + 32768;
constexpr int OFF_G   = OFF_WD + 16384;
constexpr int OFF_U   = OFF_G + 16384;
constexpr int OFF_QP  = OFF_U + 16384;
constexpr int OFF_QS  = OFF_QP + 4096;
constexpr int OFF_PS  = OFF_QS + 4 * 272;
constexpr int OFF_XN  = OFF_PS + 4 * 528;
constexpr int OFF_WMAX = OFF_XN + 1024;
constexpr int OFF_WSUM = OFF_WMAX + 256;
constexpr int OFF_GUP = OFF_WSUM + 256;
constexpr int OFF_F   = OFF_GUP + 1024;
constexpr int OFF_OS  = OFF_F + 16;
constexpr int OFF_HS  = OFF_OS + 64;
constexpr int OFF_BAR = OFF_HS + 32;
constexpr int SMEM_USED = OFF_BAR + 64 * 8;
constexpr int SMEM_BYTES = SMEM_USED + 1024;

constexpr int BAR_K = 0, BAR_V = 8, BAR_GU = 16, BAR_WD = 20, BAR_WO = 22, NBAR = 26;
#define WINDOW 8
#define PACE 344
#define PACEB PACE
#define SW 20
#define PF 8
#define ODELAY 200
#define PKV CU_TENSOR_MAP_L2_PROMOTION_L2_256B
#define PWO CU_TENSOR_MAP_L2_PROMOTION_L2_256B
#define PGU CU_TENSOR_MAP_L2_PROMOTION_L2_128B
#define PACE2 252
#define T0 544
#define QWAIT 4
#define OWAIT 18

#define ASTR 32
#define EPG 4
#define ILV 8
#define MWAIT 14
#define ROT b
struct __align__(128) Scratch {
    unsigned epoch[32];
    unsigned q[HKV * 2 * 512];
    unsigned ml[HKV * NSPLIT * 8];
    unsigned box[64 * NCTA * 8];
    unsigned long long acc[(D_MODEL / EPG) * ASTR];
};
__device__ Scratch g_scratch;

__device__ __forceinline__ uint32_t smem_u32(const void* p) { return (uint32_t)__cvta_generic_to_shared(p); }
__device__ __forceinline__ void mbar_init(uint32_t bar, uint32_t cnt) {
    asm volatile("mbarrier.init.shared::cta.b64 [%0], %1;" ::"r"(bar), "r"(cnt) : "memory");
}
__device__ __forceinline__ void mbar_expect_tx(uint32_t bar, uint32_t bytes) {
    asm volatile("mbarrier.arrive.expect_tx.shared::cta.b64 _, [%0], %1;" ::"r"(bar), "r"(bytes) : "memory");
}
__device__ __forceinline__ void mbar_wait(uint32_t bar) {
    uint32_t ok = 0; int it = 0;
    do {
        asm volatile("{\n.reg .pred p;\nmbarrier.try_wait.parity.shared::cta.b64 p, [%1], 0;\nselp.u32 %0, 1, 0, p;\n}"
                     : "=r"(ok) : "r"(bar) : "memory");
    } while (!ok && ++it < SPIN_LIMIT);
}
__device__ __forceinline__ void tma2d(uint32_t dst, const CUtensorMap* tm, int c0, int c1, uint32_t bar) {
    asm volatile("cp.async.bulk.tensor.2d.shared::cluster.global.tile.mbarrier::complete_tx::bytes [%0], [%1, {%3, %4}], [%2];"
                 ::"r"(dst), "l"(tm), "r"(bar), "r"(c0), "r"(c1) : "memory");
}
__device__ __forceinline__ void tma3d(uint32_t dst, const CUtensorMap* tm, int c0, int c1, int c2, uint32_t bar) {
    asm volatile("cp.async.bulk.tensor.3d.shared::cluster.global.tile.mbarrier::complete_tx::bytes [%0], [%1, {%3, %4, %5}], [%2];"
                 ::"r"(dst), "l"(tm), "r"(bar), "r"(c0), "r"(c1), "r"(c2) : "memory");
}
__device__ __forceinline__ void prefetch_tmap(const CUtensorMap* tm) {
    asm volatile("prefetch.tensormap [%0];" ::"l"(tm) : "memory");
}
__device__ __forceinline__ unsigned clock32() {
    unsigned t;
    asm volatile("mov.u32 %0, %%clock;" : "=r"(t)::"memory");
    return t;
}
__device__ __forceinline__ unsigned pace_time() {
    unsigned t;
    asm volatile("mov.u32 %0, %%globaltimer_lo;" : "=r"(t)::"memory");
    return t;
}
__device__ __forceinline__ bool elect_one() {
    uint32_t p;
    asm volatile("{\n.reg .pred p;\nelect.sync _|p, 0xffffffff;\nselp.u32 %0, 1, 0, p;\n}" : "=r"(p));
    return p != 0;
}
__device__ __forceinline__ void bar_sync(int id, int n) { asm volatile("bar.sync %0, %1;" ::"r"(id), "r"(n) : "memory"); }
__device__ __forceinline__ void bar_arrive(int id, int n) { asm volatile("bar.arrive %0, %1;" ::"r"(id), "r"(n) : "memory"); }

__device__ __forceinline__ void cp_async16(uint32_t dst, const void* src) {
    asm volatile("cp.async.cg.shared.global [%0], [%1], 16;" ::"r"(dst), "l"(src) : "memory");
}
__device__ __forceinline__ uint4 ldg_cached(const void* p) {
    uint4 v;
    asm volatile("ld.global.v4.u32 {%0,%1,%2,%3}, [%4];" : "=r"(v.x), "=r"(v.y), "=r"(v.z), "=r"(v.w) : "l"(p) : "memory");
    return v;
}
__device__ __forceinline__ uint4 ld_poll4(const unsigned* p) {
    uint4 v;
    asm volatile("ld.relaxed.gpu.global.v4.u32 {%0,%1,%2,%3}, [%4];" : "=r"(v.x), "=r"(v.y), "=r"(v.z), "=r"(v.w) : "l"(p) : "memory");
    return v;
}
__device__ __forceinline__ void st_pub(unsigned* p, unsigned v) {
    asm volatile("st.relaxed.gpu.global.u32 [%0], %1;" ::"l"(p), "r"(v) : "memory");
}
__device__ __forceinline__ unsigned tag_bad(const uint4& v, unsigned tag) {
    return ((v.x ^ tag) | (v.y ^ tag) | (v.z ^ tag) | (v.w ^ tag)) & 15u;
}
__device__ __forceinline__ unsigned tagged(float v, unsigned tag) { return (__float_as_uint(v) & ~15u) | tag; }
__device__ __forceinline__ float untag(unsigned v) { return __uint_as_float(v & ~15u); }

__device__ __forceinline__ void ldsm4(uint32_t (&r)[4], uint32_t addr) {
    asm volatile("ldmatrix.sync.aligned.m8n8.x4.shared.b16 {%0,%1,%2,%3}, [%4];"
                 : "=r"(r[0]), "=r"(r[1]), "=r"(r[2]), "=r"(r[3]) : "r"(addr) : "memory");
}
__device__ __forceinline__ void ldsm4t(uint32_t (&r)[4], uint32_t addr) {
    asm volatile("ldmatrix.sync.aligned.m8n8.x4.trans.shared.b16 {%0,%1,%2,%3}, [%4];"
                 : "=r"(r[0]), "=r"(r[1]), "=r"(r[2]), "=r"(r[3]) : "r"(addr) : "memory");
}
__device__ __forceinline__ void mma16816(float (&c)[4], const uint32_t (&a)[4], uint32_t b0, uint32_t b1) {
    asm volatile("mma.sync.aligned.m16n8k16.row.col.f32.bf16.bf16.f32 {%0,%1,%2,%3}, {%4,%5,%6,%7}, {%8,%9}, {%0,%1,%2,%3};"
                 : "+f"(c[0]), "+f"(c[1]), "+f"(c[2]), "+f"(c[3])
                 : "r"(a[0]), "r"(a[1]), "r"(a[2]), "r"(a[3]), "r"(b0), "r"(b1));
}
__device__ __forceinline__ float bfr(float v) { return __bfloat162float(__float2bfloat16_rn(v)); }
__device__ __forceinline__ float bflo(uint32_t v) { return __uint_as_float(v << 16); }
__device__ __forceinline__ float bfhi(uint32_t v) { return __uint_as_float(v & 0xffff0000u); }
__device__ __forceinline__ uint32_t pack_bf(float lo, float hi) {
    uint32_t r;
    asm("cvt.rn.bf16x2.f32 %0, %1, %2;" : "=r"(r) : "f"(hi), "f"(lo));
    return r;
}
__device__ __forceinline__ float fsel(bool p, float a, float b) {
    float r;
    asm("{\n.reg .pred p;\nsetp.ne.u32 p, %3, 0;\nselp.f32 %0, %1, %2, p;\n}" : "=f"(r) : "f"(a), "f"(b), "r"((unsigned)p));
    return r;
}
__device__ __forceinline__ uint32_t ucomp(const uint4& v, int j) { return j == 0 ? v.x : j == 1 ? v.y : j == 2 ? v.z : v.w; }

template <bool BF16_VALUE>
__device__ __forceinline__ bool contribute(unsigned long long* acc, __nv_bfloat16* dst, float val, unsigned mask) {
    bool fits = __any_sync(mask, fabsf(val) >= 0x1p-12f);
    if (BF16_VALUE) fits |= __all_sync(mask, fabsf(val) >= 0x1p-23f || val == 0.f);
    fits &= __all_sync(mask, fabsf(val) < 0x1p9f);
    unsigned long long add = ((unsigned long long)__float2ll_rn(fmaf(val, 0x1p46f, 0x1p15f)) & ~0xffffull) | 1u;
    if (!fits) {
        asm volatile("red.relaxed.gpu.global.add.f32 [%0], %1;" ::"l"(acc + EPG), "f"(val) : "memory");
        asm volatile("fence.acq_rel.gpu;" ::: "memory");
        add = 257u;
    }
    unsigned long long tot;
    asm volatile("atom.relaxed.gpu.global.add.u64 %0, [%1], %2;" : "=&l"(tot) : "l"(acc), "l"(add) : "memory");
    tot += add;
    const bool last = ((unsigned)tot & 255u) == NCTA + 1;
    if (last) {
        float z = __ll2float_rn((long long)(tot & ~0xffffull)) * 0x1p-46f;
        if ((unsigned)tot & 0xff00u) {
            float y;
            asm volatile("fence.acq_rel.gpu;" ::: "memory");
            asm volatile("atom.relaxed.gpu.global.exch.b32 %0, [%1], 0;" : "=f"(y) : "l"(acc + EPG) : "memory");
            z += y;
        }
        *dst = __float2bfloat16_rn(z);
        *acc = 0;
    }
    return last;
}

__global__ void __launch_bounds__(NTHREADS, 1)
fused_decode_kernel(const __nv_bfloat16* __restrict__ x, const __nv_bfloat16* __restrict__ wq,
                    __nv_bfloat16* __restrict__ out, Scratch* __restrict__ sc_,
                    const __grid_constant__ CUtensorMap tmK, const __grid_constant__ CUtensorMap tmV,
                    const __grid_constant__ CUtensorMap tmG, const __grid_constant__ CUtensorMap tmU,
                    const __grid_constant__ CUtensorMap tmWD, const __grid_constant__ CUtensorMap tmWO)
{
    extern __shared__ unsigned char smem_raw[];
    const uint32_t sraw = smem_u32(smem_raw);
    const uint32_t sb = (sraw + 1023u) & ~1023u;
    unsigned char* sp = smem_raw + (sb - sraw);

    const int tid = threadIdx.x;
    const int lane = tid & 31;
    const int b = blockIdx.x, r = b >> 4, c = b & 15;
    uint4 xa, xb;
    unsigned epoch;
    if (threadIdx.x == 0) asm volatile("cp.async.bulk.prefetch.L2.global [%0], %1;" ::"l"(wq + blockIdx.x * 16384), "n"(PF * 1024) : "memory");
    if (tid < 512) {
        const char* src = reinterpret_cast<const char*>(wq) + ((b & 1) << 21) + ((b >> 1) << 7) + (((tid >> 3) << 13) | ((tid & 7) << 4));
        const uint32_t dst = sb + OFF_WO + ((tid << 4) ^ ((tid << 1) & 16));
#pragma unroll
        for (int i = 0; i < 4; i++) cp_async16((dst ^ (32 * i)) + 8192 * i, src + (i << 19));
        asm volatile("cp.async.commit_group;" ::: "memory");
    } else if (tid >= 544) {
        xa = ldg_cached(reinterpret_cast<const uint4*>(x) + lane);
        xb = ldg_cached(reinterpret_cast<const uint4*>(x) + 32 + lane);
        asm volatile("ld.global.u32 %0, [%1];" : "=r"(epoch) : "l"(sc_->epoch) : "memory");
    }
    const int w = __shfl_sync(0xffffffffu, tid >> 5, 0);
    const bool has_ffn = (b & 7) != 7;
    const int fg = (b >> 3) * 7 + (b & 7);

    if (w == 16) {
        const unsigned t_start = pace_time();
        const bool leader = elect_one();
        if (leader) {
            prefetch_tmap(&tmK);
#pragma unroll
            for (int i = 0; i < NBAR; i++) mbar_init(sb + OFF_BAR + 8 * i, 1);
            asm volatile("fence.mbarrier_init.release.cluster;" ::: "memory");
        }
        __syncwarp();
        bar_arrive(9, NTHREADS);
        if (leader) { prefetch_tmap(&tmV); prefetch_tmap(&tmG); prefetch_tmap(&tmU); prefetch_tmap(&tmWD); prefetch_tmap(&tmWO); }
        const int row0 = r * SK + (SK - WIN) + (c / ILV) * (ILV * KEYS) + (c % ILV) * 32;
#pragma unroll
        for (int i = 0; i < NBAR; i++) {
            const bool ffn_chunk = i >= BAR_GU && i < BAR_WO;
            if (ffn_chunk && !has_ffn) continue;
            const int dep = i - WINDOW;
            if (dep >= -4 && dep < 0) bar_sync(5 + dep + 4, 160);
            else if (dep >= 0) {
                if (i >= BAR_WO && !has_ffn) { if (dep - 6 < BAR_GU) mbar_wait(sb + OFF_BAR + 8 * (dep - 6)); else mbar_wait(sb + OFF_BAR + 8 * dep); }
                else mbar_wait(sb + OFF_BAR + 8 * dep);
            }
            {
                const int slot = (i >= BAR_WO && !has_ffn) ? i - 6 : i;
                const unsigned due = T0 + (slot < 16 ? slot * PACE : slot <= SW ? 15 * PACE + (slot - 15) * PACEB : 15 * PACE + (SW - 15) * PACEB + (slot - SW) * PACE2);
                for (int it = 0; pace_time() - t_start < due && it < (1 << 14); it++) {}
            }
            if (leader) {
                if (i == BAR_WO) asm volatile("fence.proxy.async.shared::cta;" ::: "memory");
                const int blk = (i - BAR_WO + (ROT)) & 3;
                const uint32_t bar = sb + OFF_BAR + 8 * (i < BAR_WO ? i : BAR_WO + blk);
                mbar_expect_tx(bar, 8192);
                if (i < 8)       tma3d(sb + OFF_K + i * 8192, &tmK, 0, row0 + 32 * ILV * i, 0, bar);
                else if (i < 16) tma3d(sb + OFF_V + (i - 8) * 8192, &tmV, 0, row0 + 32 * ILV * (i - 8), 0, bar);
                else if (i < 18) tma2d(sb + OFF_G + (i - 16) * 8192, &tmG, 16 * fg, 256 * (i - 16), bar);
                else if (i < 20) tma2d(sb + OFF_U + (i - 18) * 8192, &tmU, 16 * fg, 256 * (i - 18), bar);
                else if (i < 22) tma3d(sb + OFF_WD + (i - 20) * 8192, &tmWD, 0, 16 * fg, 4 * (i - 20), bar);
                else             tma3d(sb + OFF_WO + blk * 8192, &tmWO, 0, 32 * b, 2 * blk, bar);
            }
        }
        return;
    }

    if (w == 17) {
        float v[16];
#pragma unroll
        for (int j = 0; j < 4; j++) {
            v[2 * j] = bflo(ucomp(xa, j)); v[2 * j + 1] = bfhi(ucomp(xa, j));
            v[8 + 2 * j] = bflo(ucomp(xb, j)); v[8 + 2 * j + 1] = bfhi(ucomp(xb, j));
        }
        float s = (((v[0] + v[1]) + (v[2] + v[3])) + ((v[4] + v[5]) + (v[6] + v[7]))) +
                  (((v[8] + v[9]) + (v[10] + v[11])) + ((v[12] + v[13]) + (v[14] + v[15])));
#pragma unroll
        for (int o = 16; o > 0; o >>= 1) s += __shfl_xor_sync(0xffffffffu, s, o);
        const float mean = s * (1.0f / D_MODEL);
        float q4[4] = {0.f, 0.f, 0.f, 0.f};
#pragma unroll
        for (int j = 0; j < 16; j++) { const float d = v[j] - mean; q4[j & 3] = fmaf(d, d, q4[j & 3]); }
        float q2 = (q4[0] + q4[1]) + (q4[2] + q4[3]);
#pragma unroll
        for (int o = 16; o > 0; o >>= 1) q2 += __shfl_xor_sync(0xffffffffu, q2, o);
        const float mean_b = bfr(mean);
        const float sd_b = bfr(sqrtf(bfr(bfr(q2 * (1.0f / D_MODEL)) + 1e-5f)));
        const float rinv = 1.0f / sd_b;
        uint32_t n[8];
#pragma unroll
        for (int j = 0; j < 8; j++) n[j] = pack_bf(bfr(v[2 * j] - mean_b) * rinv, bfr(v[2 * j + 1] - mean_b) * rinv);
        *reinterpret_cast<uint4*>(sp + OFF_XN + 16 * lane) = make_uint4(n[0], n[1], n[2], n[3]);
        *reinterpret_cast<uint4*>(sp + OFF_XN + 512 + 16 * lane) = make_uint4(n[4], n[5], n[6], n[7]);
        const unsigned tag = (2u * epoch + 2u) & 15u;
        if (lane == 0) *reinterpret_cast<uint2*>(sp + OFF_F) = make_uint2(tag, epoch);
        bar_sync(9, NTHREADS);
        if (lane < 4) {
            const int col = 4 * b + lane;
            if (contribute<true>(&sc_->acc[(col / EPG) * ASTR + col % EPG], out + col, __bfloat162float(x[col]), 15u) && col == 0) st_pub(sc_->epoch, epoch + 1u);
        }
        __syncwarp();
        {
            mbar_wait(sb + OFF_BAR + 8 * MWAIT);
            const unsigned* srcm = &sc_->ml[128 * r + 8 * (lane & 15) + 4 * (c >> 3)];
            uint4 u; int it = 0;
            do { u = ld_poll4(srcm); } while (tag_bad(u, tag) && ++it < SPIN_LIMIT);
            __syncwarp();
            float fw[4];
            {
                const float m = untag((c & 4) ? u.y : u.x);
                float G = m;
#pragma unroll
                for (int o = 1; o < 16; o <<= 1) G = fmaxf(G, __shfl_xor_sync(0xffffffffu, G, o));
                const float e = __expf(m - G);
                float Ls = untag((c & 4) ? u.w : u.z) * e;
#pragma unroll
                for (int o = 1; o < 16; o <<= 1) Ls += __shfl_xor_sync(0xffffffffu, Ls, o);
                const float f = e / Ls;
#pragma unroll
                for (int i = 0; i < 4; i++) fw[i] = __shfl_sync(0xffffffffu, f, (lane >> 3) + 4 * i);
            }
            const unsigned* src = &sc_->box[((lane >> 1) * NCTA + b) * 8 + 4 * (lane & 1)];
            mbar_wait(sb + OFF_BAR + 8 * (has_ffn ? OWAIT : BAR_WO + ((OWAIT - BAR_GU + (ROT)) & 3)));
            { const unsigned t1 = clock32(); for (int it = 0; clock32() - t1 < ODELAY && it < (1 << 12); it++) {} }
            uint4 v[4];
            do {
#pragma unroll
                for (int i = 0; i < 4; i++) v[i] = ld_poll4(src + i * (16 * NCTA * 8));
            } while ((tag_bad(v[0], tag) | tag_bad(v[1], tag) | tag_bad(v[2], tag) | tag_bad(v[3], tag)) && ++it < SPIN_LIMIT);
            __syncwarp();
            float o0 = fmaf(untag(v[0].x), fw[0], untag(v[1].x) * fw[1]) + fmaf(untag(v[2].x), fw[2], untag(v[3].x) * fw[3]);
            float o1 = fmaf(untag(v[0].y), fw[0], untag(v[1].y) * fw[1]) + fmaf(untag(v[2].y), fw[2], untag(v[3].y) * fw[3]);
            float o2 = fmaf(untag(v[0].z), fw[0], untag(v[1].z) * fw[1]) + fmaf(untag(v[2].z), fw[2], untag(v[3].z) * fw[3]);
            float o3 = fmaf(untag(v[0].w), fw[0], untag(v[1].w) * fw[1]) + fmaf(untag(v[2].w), fw[2], untag(v[3].w) * fw[3]);
#pragma unroll
            for (int o = 8; o < 32; o <<= 1) {
                o0 += __shfl_xor_sync(0xffffffffu, o0, o); o1 += __shfl_xor_sync(0xffffffffu, o1, o);
                o2 += __shfl_xor_sync(0xffffffffu, o2, o); o3 += __shfl_xor_sync(0xffffffffu, o3, o);
            }
            if (lane < 8) *reinterpret_cast<uint2*>(sp + OFF_OS + 8 * lane) = make_uint2(pack_bf(o0, o1), pack_bf(o2, o3));
            __syncwarp();
            bar_arrive(3, 544);
        }
        return;
    }

    const int g = lane >> 2, t = lane & 3;

    asm volatile("cp.async.wait_group 0;" ::: "memory");
    bar_arrive(5 + (w >> 2), 160);
    bar_sync(9, NTHREADS);
    const unsigned tag = *reinterpret_cast<const unsigned*>(sp + OFF_F);
    const uint2 xn = *reinterpret_cast<const uint2*>(sp + OFF_XN + 2 * (256 * (c & 1) + 64 * t + 4 * w));
    {
        float qa[4][4];
        const uint32_t base = sb + OFF_WO + 8192 * ((lane >> 1) & 3) + 512 * w + 128 * ((lane & 1) + 2 * (lane >> 4));
#pragma unroll
        for (int j = 0; j < 4; j++) {
            uint32_t a[4];
            ldsm4t(a, base + (((2 * j + ((lane >> 3) & 1)) ^ (lane & 7)) << 4));
            qa[j][0] = qa[j][1] = qa[j][2] = qa[j][3] = 0.f;
            mma16816(qa[j], a, xn.x, xn.y);
        }
        float v0 = qa[0][0], v1 = qa[0][2];
#pragma unroll
        for (int j = 1; j < 4; j++)
            if (t == j) { v0 = qa[j][0]; v1 = qa[j][2]; }
        float* qp = reinterpret_cast<float*>(sp + OFF_QP) + 64 * w + 16 * t + g;
        qp[0] = v0; qp[8] = v1;
    }
    bar_sync(1, 512);
    if (w < 2) {
        const float* qp = reinterpret_cast<const float*>(sp + OFF_QP) + tid;
        float s0 = 0.f, s1 = 0.f, s2 = 0.f, s3 = 0.f;
#pragma unroll
        for (int p = 0; p < 16; p += 4) { s0 += qp[64 * p]; s1 += qp[64 * p + 64]; s2 += qp[64 * p + 128]; s3 += qp[64 * p + 192]; }
        st_pub(&sc_->q[1024 * r + 512 * (c & 1) + 64 * (c >> 1) + tid], tagged((s0 + s1) + (s2 + s3), tag));
    } else if (w >= 4 && w < 8) {
        const int i = tid - 128;
        const unsigned* src = &sc_->q[1024 * r + 4 * i];
        uint4 v, u; int it = 0;
        if (QWAIT >= 0) mbar_wait(sb + OFF_BAR + 8 * QWAIT);
        do { v = ld_poll4(src); u = ld_poll4(src + 512); } while ((tag_bad(v, tag) | tag_bad(u, tag)) && ++it < SPIN_LIMIT);
        *reinterpret_cast<uint2*>(sp + OFF_QS + (i >> 5) * 272 + 8 * (i & 31)) =
            make_uint2(pack_bf(untag(v.x) + untag(u.x), untag(v.y) + untag(u.y)), pack_bf(untag(v.z) + untag(u.z), untag(v.w) + untag(u.w)));
    }
    bar_sync(2, 512);

    float M0, M1;
    {
        uint32_t qb[4][4];
#pragma unroll
        for (int i = 0; i < 4; i++) ldsm4(qb[i], sb + OFF_QS + (lane & 3) * 272 + (4 * i + (lane >> 3)) * 16);
        mbar_wait(sb + OFF_BAR + 8 * (BAR_K + (w >> 1)));
        const int key = 16 * (w & 1) + (lane & 7) + 8 * ((lane >> 3) & 1);
        const uint32_t kbase = sb + OFF_K + (w >> 1) * 8192 + key * 128;
        float sa[4] = {0.f, 0.f, 0.f, 0.f}, sc[4] = {0.f, 0.f, 0.f, 0.f};
#pragma unroll
        for (int ks = 0; ks < 8; ks++) {
            uint32_t a[4];
            const int ch = 2 * (ks & 3) + (lane >> 4);
            ldsm4(a, kbase + (ks >> 2) * 4096 + ((ch ^ (lane & 7)) << 4));
            if (ks & 1) mma16816(sc, a, qb[ks >> 1][2], qb[ks >> 1][3]);
            else        mma16816(sa, a, qb[ks >> 1][0], qb[ks >> 1][1]);
        }
        const float scale = 0.088388347648318447f;
        float s[4];
#pragma unroll
        for (int k = 0; k < 4; k++) s[k] = bfr(bfr(sa[k] + sc[k]) * scale);
        float m0 = fmaxf(s[0], s[2]), m1 = fmaxf(s[1], s[3]);
#pragma unroll
        for (int o = 4; o < 32; o <<= 1) {
            m0 = fmaxf(m0, __shfl_xor_sync(0xffffffffu, m0, o));
            m1 = fmaxf(m1, __shfl_xor_sync(0xffffffffu, m1, o));
        }
        if (lane < 2) *reinterpret_cast<float2*>(sp + OFF_WMAX + 16 * w + 8 * lane) = make_float2(m0, m1);
        bar_sync(2, 512);
        const float2 mm = *reinterpret_cast<const float2*>(sp + OFF_WMAX + 8 * lane);
        M0 = mm.x; M1 = mm.y;
#pragma unroll
        for (int o = 2; o < 32; o <<= 1) {
            M0 = fmaxf(M0, __shfl_xor_sync(0xffffffffu, M0, o));
            M1 = fmaxf(M1, __shfl_xor_sync(0xffffffffu, M1, o));
        }
        const bool up = t >= 2;
        float pa = __expf((up ? s[2] : s[0]) - M0), pb = __expf((up ? s[3] : s[1]) - M1);
        const int pk = 16 * w + g + (up ? 8 : 0);
        __nv_bfloat16* ps = reinterpret_cast<__nv_bfloat16*>(sp + OFF_PS) + 2 * (t & 1) * 264 + pk;
        ps[0] = __float2bfloat16_rn(pa);
        ps[264] = __float2bfloat16_rn(pb);
#pragma unroll
        for (int o = 2; o < 32; o <<= 1) {
            pa += __shfl_xor_sync(0xffffffffu, pa, o);
            pb += __shfl_xor_sync(0xffffffffu, pb, o);
        }
        if (lane < 2) *reinterpret_cast<float2*>(sp + OFF_WSUM + 16 * w + 8 * lane) = make_float2(pa, pb);
        bar_sync(2, 512);
    }

    if (w < 8) {
        uint32_t pb[8][4];
#pragma unroll
        for (int i = 0; i < 8; i++) ldsm4(pb[i], sb + OFF_PS + (lane & 3) * 528 + (4 * i + (lane >> 3)) * 16);
        const int dch = 2 * (w & 3) + ((lane >> 3) & 1);
        const uint32_t vbase = sb + OFF_V + (w >> 2) * 4096 + ((lane & 7) + 8 * (lane >> 4)) * 128 + ((dch ^ (lane & 7)) << 4);
        float oa[4] = {0.f, 0.f, 0.f, 0.f}, ob[4] = {0.f, 0.f, 0.f, 0.f};
#pragma unroll
        for (int vc = 0; vc < 8; vc++) {
            mbar_wait(sb + OFF_BAR + 8 * (BAR_V + vc));
#pragma unroll
            for (int kk = 0; kk < 2; kk++) {
                uint32_t a[4];
                ldsm4t(a, vbase + vc * 8192 + kk * 2048);
                const int ks = 2 * vc + kk;
                if (ks & 1) mma16816(ob, a, pb[ks >> 1][2], pb[ks >> 1][3]);
                else        mma16816(oa, a, pb[ks >> 1][0], pb[ks >> 1][1]);
            }
        }
        const bool up = t >= 2;
        const float va = up ? oa[2] + ob[2] : oa[0] + ob[0];
        const float vb = up ? oa[3] + ob[3] : oa[1] + ob[1];
        unsigned* dst = &sc_->box[((4 * c + 2 * (w & 1) + (t >> 1)) * NCTA + 16 * r + 8 * (t & 1) + (w >> 1)) * 8 + g];
        st_pub(dst, tagged(va, tag));
        st_pub(dst + 4 * 8, tagged(vb, tag));
    } else {
        if (w == 8) {
            const float2 ss = *reinterpret_cast<const float2*>(sp + OFF_WSUM + 8 * lane);
            float l0 = ss.x, l1 = ss.y;
#pragma unroll
            for (int o = 2; o < 32; o <<= 1) {
                l0 += __shfl_xor_sync(0xffffffffu, l0, o);
                l1 += __shfl_xor_sync(0xffffffffu, l1, o);
            }
            if (lane < 2) {
                unsigned* dst = &sc_->ml[8 * b + 4 * lane];
                asm volatile("st.relaxed.gpu.global.v4.u32 [%0], {%1,%2,%3,%4};" ::"l"(dst),
                             "r"(tagged(M0, tag)), "r"(tagged(M1, tag)), "r"(tagged(l0, tag)), "r"(tagged(l1, tag)) : "memory");
            }
        }
        if (has_ffn) {
            const int wi = w - 8;
            uint32_t xb0[4], xb1[4];
#pragma unroll
            for (int ks = 0; ks < 4; ks++) {
                xb0[ks] = *reinterpret_cast<const uint32_t*>(sp + OFF_XN + 2 * (64 * wi + 16 * ks + 2 * t));
                xb1[ks] = *reinterpret_cast<const uint32_t*>(sp + OFF_XN + 2 * (64 * wi + 16 * ks + 8 + 2 * t));
            }
            const uint32_t gbase = sb + OFF_G + (64 * wi + (lane & 7) + 8 * (lane >> 4)) * 32 + ((((lane >> 3) ^ (lane >> 2)) & 1) << 4);
            float ga[4] = {0.f, 0.f, 0.f, 0.f}, ua[4] = {0.f, 0.f, 0.f, 0.f};
            mbar_wait(sb + OFF_BAR + 8 * (BAR_GU + (wi >> 2)));
            mbar_wait(sb + OFF_BAR + 8 * (BAR_GU + 2 + (wi >> 2)));
#pragma unroll
            for (int ks = 0; ks < 4; ks++) {
                uint32_t a[4], a2[4];
                ldsm4t(a, gbase + ks * 512);
                ldsm4t(a2, gbase + 16384 + ks * 512);
                mma16816(ga, a, xb0[ks], xb1[ks]);
                mma16816(ua, a2, xb0[ks], xb1[ks]);
            }
            const float val = t == 0 ? ga[0] : t == 1 ? ga[2] : t == 2 ? ua[0] : ua[2];
            *reinterpret_cast<float*>(sp + OFF_GUP + 4 * (32 * wi + 8 * t + g)) = val;
            if (w == 9) {
                bar_sync(4, 256);
                const float* gp = reinterpret_cast<const float*>(sp + OFF_GUP) + lane;
                float s = ((gp[0] + gp[32]) + (gp[64] + gp[96])) + ((gp[128] + gp[160]) + (gp[192] + gp[224]));
                s = bfr(s);
                const float uu = __shfl_down_sync(0xffffffffu, s, 16);
                const float sg = bfr(s / (1.0f + __expf(-s)));
                if (lane < 16) *reinterpret_cast<__nv_bfloat16*>(sp + OFF_HS + 2 * lane) = __float2bfloat16_rn(sg * uu);
            } else {
                bar_arrive(4, 256);
            }
        }
    }
    bar_sync(3, 544);

    {
        float c0[4] = {0.f, 0.f, 0.f, 0.f}, c1[4] = {0.f, 0.f, 0.f, 0.f};
        const int rowl = (lane & 7) + 8 * (lane >> 4);
        const int ch0 = 4 * (w & 1) + ((lane >> 3) & 1);
        const uint32_t sw0 = (ch0 ^ (lane & 7)) << 4, sw1 = ((ch0 + 2) ^ (lane & 7)) << 4;
        uint32_t ob[4];
#pragma unroll
        for (int i = 0; i < 4; i++) ob[i] = *reinterpret_cast<const uint32_t*>(sp + OFF_OS + 16 * i + 4 * t);
        if (has_ffn) {
            const uint32_t h0 = *reinterpret_cast<const uint32_t*>(sp + OFF_HS + 4 * t);
            const uint32_t h1 = *reinterpret_cast<const uint32_t*>(sp + OFF_HS + 16 + 4 * t);
            const uint32_t base = sb + OFF_WD + (w >> 1) * 2048 + rowl * 128;
            mbar_wait(sb + OFF_BAR + 8 * (BAR_WD + (w >> 3)));
            uint32_t a[4], a2[4];
            ldsm4t(a, base + sw0);
            ldsm4t(a2, base + sw1);
            mma16816(c0, a, h0, h1);
            mma16816(c1, a2, h0, h1);
        }
        uint32_t base0 = sb + OFF_WO + (w >> 1) * 4096 + rowl * 128 + sw0, base1 = base0 - sw0 + sw1;
        const unsigned col = 32 * w + 8 * t + g;
        unsigned long long* acc = &sc_->acc[(col / EPG) * ASTR + col % EPG];
        __nv_bfloat16* dst = out + col;
        asm volatile("" : "+l"(acc), "+l"(dst), "+r"(base0), "+r"(base1));
        mbar_wait(sb + OFF_BAR + 8 * (BAR_WO + (w >> 2)));
        uint32_t a0[4], a1[4], a2[4], a3[4];
        float d0[4] = {0.f, 0.f, 0.f, 0.f}, d1[4] = {0.f, 0.f, 0.f, 0.f};
        ldsm4t(a0, base0);
        ldsm4t(a1, base1);
        ldsm4t(a2, base0 + 2048);
        ldsm4t(a3, base1 + 2048);
        mma16816(c0, a0, ob[0], ob[1]);
        mma16816(c1, a1, ob[0], ob[1]);
        mma16816(d0, a2, ob[2], ob[3]);
        mma16816(d1, a3, ob[2], ob[3]);
        const bool t1 = t & 1, t2 = t & 2;
        const float val = fsel(t2, fsel(t1, c1[2], c1[0]), fsel(t1, c0[2], c0[0])) + fsel(t2, fsel(t1, d1[2], d1[0]), fsel(t1, d0[2], d0[0]));
        if (contribute<false>(acc, dst, val, 0xffffffffu) && col == 0)
            st_pub(sc_->epoch, *reinterpret_cast<const unsigned*>(sp + OFF_F + 4) + 1u);
    }
}

typedef CUresult (*EncodeFn)(CUtensorMap*, CUtensorMapDataType, cuuint32_t, void*, const cuuint64_t*, const cuuint64_t*,
                             const cuuint32_t*, const cuuint32_t*, CUtensorMapInterleave, CUtensorMapSwizzle,
                             CUtensorMapL2promotion, CUtensorMapFloatOOBfill);

void encode(EncodeFn fn, CUtensorMap* m, void* base, int rank, const cuuint64_t* dims, const cuuint64_t* strides,
            const cuuint32_t* box, CUtensorMapSwizzle sw, CUtensorMapL2promotion promo) {
    const cuuint32_t es[3] = {1, 1, 1};
    fn(m, CU_TENSOR_MAP_DATA_TYPE_BFLOAT16, rank, base, dims, strides, box, es, CU_TENSOR_MAP_INTERLEAVE_NONE, sw, promo,
       CU_TENSOR_MAP_FLOAT_OOB_FILL_NONE);
}

}

extern "C" void kernel_launch(void* const* d_in, const int* in_sizes, int n_in, void* d_out, int out_size) {
    (void)in_sizes; (void)n_in; (void)out_size;
    static EncodeFn fn = nullptr;
    static Scratch* scratch = nullptr;
    if (!fn) {
        void* p = nullptr;
        cudaDriverEntryPointQueryResult st;
        cudaGetDriverEntryPoint("cuTensorMapEncodeTiled", &p, cudaEnableDefault, &st);
        fn = (EncodeFn)p;
        cudaGetSymbolAddress((void**)&scratch, g_scratch);
        cudaFuncSetAttribute(fused_decode_kernel, cudaFuncAttributeMaxDynamicSharedMemorySize, SMEM_BYTES);
    }
    CUtensorMap tmK, tmV, tmG, tmU, tmWD, tmWO;
    {
        const cuuint64_t dims[3] = {64, (cuuint64_t)HKV * SK, 2};
        const cuuint64_t str[2] = {256, 128};
        const cuuint32_t box[3] = {64, 32, 2};
        encode(fn, &tmK, d_in[1], 3, dims, str, box, CU_TENSOR_MAP_SWIZZLE_128B, PKV);
        encode(fn, &tmV, d_in[2], 3, dims, str, box, CU_TENSOR_MAP_SWIZZLE_128B, PKV);
    }
    {
        const cuuint64_t dims[2] = {FF, D_MODEL};
        const cuuint64_t str[1] = {FF * 2};
        const cuuint32_t box[2] = {16, 256};
        encode(fn, &tmG, d_in[6], 2, dims, str, box, CU_TENSOR_MAP_SWIZZLE_32B, PGU);
        encode(fn, &tmU, d_in[7], 2, dims, str, box, CU_TENSOR_MAP_SWIZZLE_32B, PGU);
    }
    {
        const cuuint64_t dimsD[3] = {64, FF, 8}, dimsO[3] = {64, 32 * DH, 8};
        const cuuint64_t str[2] = {1024, 128};
        const cuuint32_t boxD[3] = {64, 16, 4}, boxO[3] = {64, 32, 2};
        encode(fn, &tmWD, d_in[8], 3, dimsD, str, boxD, CU_TENSOR_MAP_SWIZZLE_128B, PWO);
        encode(fn, &tmWO, d_in[4], 3, dimsO, str, boxO, CU_TENSOR_MAP_SWIZZLE_128B, PWO);
    }
    fused_decode_kernel<<<NCTA, NTHREADS, SMEM_BYTES, cudaStreamPerThread>>>(
        (const __nv_bfloat16*)d_in[0], (const __nv_bfloat16*)d_in[3], (__nv_bfloat16*)d_out, scratch, tmK, tmV, tmG, tmU, tmWD, tmWO);
}
```
